```python
import torch

def _softmax(x, axis=-1):
    return torch.softmax(x, dim=axis)

def _gelu(x):
    return torch.nn.functional.gelu(x, approximate='tanh')

def _silu(x):
    return torch.nn.functional.silu(x)

def _sigmoid(x):
    return torch.sigmoid(x)

def _layernorm(x, axis=-1, eps=1e-05):
    m = x.mean(dim=axis, keepdim=True)
    v = x.var(dim=axis, keepdim=True, unbiased=False)
    return (x - m) / torch.sqrt(v + eps)

def _scatter_add(tgt, idx, src, axis=0):
    return tgt.clone().index_add_(axis, idx, src)

def _segment_sum(src, seg, n):
    out = torch.zeros((n,) + src.shape[1:], dtype=src.dtype)
    return out.index_add_(0, seg, src)

def _pad(x, pw):
    flat = tuple((v for pair in reversed(pw) for v in pair))
    return torch.nn.functional.pad(x, flat)
kernel_name = 'recurrent_scan__memory_aug_recurrent_mem_tr__mixer_gmlp__prompt'

def setup_inputs():

    _w = lambda a: (lambda t: t.to(torch.bfloat16) if t.is_floating_point() else t)(torch.as_tensor(a))

    def _A_setup():
        B, S, Dm = (1, 2048, 640)
        H, Dh = (32, 128)
        M, seg = (8, 32)
        seg = min(seg, S)
        S = S // seg * seg
        return {'x': _w((lambda *s: torch.randn(*s, dtype=torch.bfloat16) * 0.05)(B, S, Dm)), 'mem0': _w((lambda *s: torch.randn(*s, dtype=torch.bfloat16) * 0.2)(B, M, Dm)), 'Wq': _w((lambda *s: torch.randn(*s, dtype=torch.bfloat16) * 0.8)(Dm, H, Dh) * Dm ** (-0.5)), 'Wk': _w((lambda *s: torch.randn(*s, dtype=torch.bfloat16) * 0.8)(Dm, H, Dh) * Dm ** (-0.5)), 'Wv': _w((lambda *s: torch.randn(*s, dtype=torch.bfloat16) * 0.2)(Dm, H, Dh) * Dm ** (-0.5)), 'Wo': _w((lambda *s: torch.randn(*s, dtype=torch.bfloat16) * 0.2)(H, Dh, Dm) * (H * Dh) ** (-0.5)), 'seg_len': seg}
    _A_in = _A_setup()

    def _B_setup():
        B, S, D, F = (1, 2048, 640, 1728)
        Fh = F // 2
        return {'x': _w((lambda *s: torch.randn(*s, dtype=torch.bfloat16) * 0.05)(B, S, D)), 'w_in': _w((lambda *s: torch.randn(*s, dtype=torch.bfloat16) * 0.4)(D, 2 * Fh)), 'w_sp': _w(0.01 * (lambda *s: torch.randn(*s, dtype=torch.bfloat16) * 0.4)(S, S)), 'b_sp': _w(1.0 + 0.01 * (lambda *s: torch.randn(*s, dtype=torch.bfloat16) * 0.1)(S)), 'w_out': _w((lambda *s: torch.randn(*s, dtype=torch.bfloat16) * 0.1)(Fh, D))}
    _B_in = _B_setup()
    return {'A_x': _A_in['x'], 'A_mem0': _A_in['mem0'], 'A_Wq': _A_in['Wq'], 'A_Wk': _A_in['Wk'], 'A_Wv': _A_in['Wv'], 'A_Wo': _A_in['Wo'], 'A_seg_len': _A_in['seg_len'], 'B_x': _B_in['x'], 'B_w_in': _B_in['w_in'], 'B_w_sp': _B_in['w_sp'], 'B_b_sp': _B_in['b_sp'], 'B_w_out': _B_in['w_out']}

def reference(A_x, A_mem0, A_Wq, A_Wk, A_Wv, A_Wo, A_seg_len, B_x, B_w_in, B_w_sp, B_b_sp, B_w_out):

    def _A_ref(x, mem0, Wq, Wk, Wv, Wo, seg_len):
        B, S, Dm = x.shape
        H, Dh = (Wq.shape[1], Wq.shape[2])
        M = mem0.shape[1]
        scale = Dh ** (-0.5)
        n_seg = S // seg_len
        L = M + seg_len
        idx = torch.arange(L)
        mask = (idx[:, None] < M) | (idx[:, None] >= idx[None, :])
        mem = mem0
        outs = []
        for s in range(n_seg):
            xs = x[:, s * seg_len:(s + 1) * seg_len, :].clone()
            h = torch.concatenate([mem, xs], axis=1)
            q = torch.einsum('btd,dhe->bhte', h, Wq)
            k = torch.einsum('btd,dhe->bhte', h, Wk)
            v = torch.einsum('btd,dhe->bhte', h, Wv)
            scores = torch.einsum('bhqe,bhke->bhqk', q, k) * scale
            scores = torch.where(mask[None, None], scores, -1000000000.0)
            p = _softmax(scores, axis=-1)
            o = torch.einsum('bhqk,bhke->bhqe', p, v)
            o = torch.einsum('bhte,hed->btd', o, Wo)
            mem = o[:, :M, :].clone()
            outs.append(o[:, M:, :])
        return torch.concatenate(outs, axis=1)

    def _B_ref(x, w_in, w_sp, b_sp, w_out):
        B, S, D = x.shape
        F = w_in.shape[-1]
        Fh = F // 2
        z = _gelu(torch.einsum('bsd,df->bsf', x, w_in))
        z1 = z[..., :Fh].clone()
        z2 = _layernorm(z[..., Fh:], axis=-1)
        g = torch.einsum('ts,bsf->btf', w_sp, z2) + b_sp[None, :, None]
        return torch.einsum('bsf,fd->bsd', z1 * g, w_out)
    x = A_x
    xn = _layernorm(x, axis=-1)
    s = _A_ref(xn, A_mem0, A_Wq, A_Wk, A_Wv, A_Wo, A_seg_len)
    g = _silu(_B_ref(xn, B_w_in, B_w_sp, B_b_sp, B_w_out))
    return x + s * g
```

```cpp
#include <cuda_runtime.h>
#include <cuda_bf16.h>
#include <cuda.h>
#include <stdint.h>

typedef __nv_bfloat16 bf16;

namespace {

constexpr int S_ = 2048, D_ = 640, H_ = 32, DH_ = 128, HD_ = 4096, MM_ = 8, SEG_ = 32, NSEG_ = 64;
constexpr int F_ = 1728, FH_ = 864;

__device__ bf16 g_xn[S_ * D_];
__device__ bf16 g_q[S_ * HD_];
__device__ bf16 g_k[S_ * HD_];
__device__ bf16 g_v[S_ * HD_];
__device__ bf16 g_z[S_ * F_];
__device__ bf16 g_z2n[S_ * FH_];
__device__ bf16 g_y[S_ * FH_];
__device__ bf16 g_gg[S_ * D_];
__device__ bf16 g_km[NSEG_ * MM_ * HD_];
__device__ bf16 g_vm[NSEG_ * MM_ * HD_];
__device__ bf16 g_o[S_ * HD_];
__device__ uint2 g_sx[2 * H_ * 4 * 320];
__device__ uint2 g_vx[2 * H_ * 4 * 128];
__device__ float g_acc[NSEG_ * D_ * MM_];
__device__ unsigned g_cnt[(NSEG_ + 1) * 32];
__device__ unsigned g_kvflag[32 * 32];
__device__ unsigned g_atflag[32 * 32];
__device__ int g_err;

__device__ __forceinline__ float bf16r(float x) { return __bfloat162float(__float2bfloat16_rn(x)); }
__device__ __forceinline__ uint32_t smem_u32(const void* p) { return (uint32_t)__cvta_generic_to_shared(p); }
__device__ __forceinline__ uint32_t pack_bf16(float a, float b) {
    __nv_bfloat162 t = __floats2bfloat162_rn(a, b);
    return *reinterpret_cast<uint32_t*>(&t);
}

__device__ __forceinline__ void mbar_init(uint32_t bar, uint32_t count) {
    asm volatile("mbarrier.init.shared::cta.b64 [%0], %1;" ::"r"(bar), "r"(count));
}
__device__ __forceinline__ void mbar_expect_tx(uint32_t bar, uint32_t bytes) {
    asm volatile("mbarrier.arrive.expect_tx.shared::cta.b64 _, [%0], %1;" ::"r"(bar), "r"(bytes) : "memory");
}
__device__ __forceinline__ void mbar_arrive(uint32_t bar) {
    asm volatile("mbarrier.arrive.shared::cta.b64 _, [%0];" ::"r"(bar) : "memory");
}
__device__ __forceinline__ void mbar_wait(uint32_t bar, uint32_t parity) {
    uint32_t done;
    do {
        asm volatile(
            "{\n .reg .pred p;\n mbarrier.try_wait.parity.shared::cta.b64 p, [%1], %2;\n selp.u32 %0, 1, 0, p;\n}\n"
            : "=r"(done)
            : "r"(bar), "r"(parity)
            : "memory");
    } while (!done);
}
__device__ __forceinline__ void tma_load_2d(uint32_t dst, const CUtensorMap* tm, int c0, int c1, uint32_t bar) {
    asm volatile(
        "cp.async.bulk.tensor.2d.shared::cluster.global.mbarrier::complete_tx::bytes [%0], [%1, {%3, %4}], [%2];" ::"r"(dst),
        "l"(tm), "r"(bar), "r"(c0), "r"(c1)
        : "memory");
}
__device__ __forceinline__ uint64_t make_desc(uint32_t saddr, uint32_t lbo, uint32_t sbo) {
    return (uint64_t)((saddr & 0x3FFFF) >> 4) | ((uint64_t)(lbo >> 4) << 16) | ((uint64_t)(sbo >> 4) << 32) |
           ((uint64_t)1 << 62);
}
__device__ __forceinline__ void wgmma_fence() { asm volatile("wgmma.fence.sync.aligned;" ::: "memory"); }
__device__ __forceinline__ void wgmma_commit() { asm volatile("wgmma.commit_group.sync.aligned;" ::: "memory"); }
template <int N>
__device__ __forceinline__ void wgmma_wait() {
    asm volatile("wgmma.wait_group.sync.aligned %0;" ::"n"(N) : "memory");
}
__device__ __forceinline__ void named_bar(int id, int n) { asm volatile("bar.sync %0, %1;" ::"r"(id), "r"(n) : "memory"); }

__device__ __forceinline__ void ldsm_x4(uint32_t& r0, uint32_t& r1, uint32_t& r2, uint32_t& r3, uint32_t addr) {
    asm volatile("ldmatrix.sync.aligned.m8n8.x4.shared.b16 {%0,%1,%2,%3}, [%4];"
                 : "=r"(r0), "=r"(r1), "=r"(r2), "=r"(r3)
                 : "r"(addr));
}
__device__ __forceinline__ void ldsm_x4_t(uint32_t& r0, uint32_t& r1, uint32_t& r2, uint32_t& r3, uint32_t addr) {
    asm volatile("ldmatrix.sync.aligned.m8n8.x4.trans.shared.b16 {%0,%1,%2,%3}, [%4];"
                 : "=r"(r0), "=r"(r1), "=r"(r2), "=r"(r3)
                 : "r"(addr));
}
__device__ __forceinline__ void ldsm_x2(uint32_t& r0, uint32_t& r1, uint32_t addr) {
    asm volatile("ldmatrix.sync.aligned.m8n8.x2.shared.b16 {%0,%1}, [%2];" : "=r"(r0), "=r"(r1) : "r"(addr));
}
__device__ __forceinline__ void ldsm_x2_t(uint32_t& r0, uint32_t& r1, uint32_t addr) {
    asm volatile("ldmatrix.sync.aligned.m8n8.x2.trans.shared.b16 {%0,%1}, [%2];" : "=r"(r0), "=r"(r1) : "r"(addr));
}
__device__ __forceinline__ void mma16816(float* c, uint32_t a0, uint32_t a1, uint32_t a2, uint32_t a3, uint32_t b0,
                                         uint32_t b1) {
    asm volatile(
        "mma.sync.aligned.m16n8k16.row.col.f32.bf16.bf16.f32 {%0,%1,%2,%3}, {%4,%5,%6,%7}, {%8,%9}, {%0,%1,%2,%3};"
        : "+f"(c[0]), "+f"(c[1]), "+f"(c[2]), "+f"(c[3])
        : "r"(a0), "r"(a1), "r"(a2), "r"(a3), "r"(b0), "r"(b1));
}
__device__ __forceinline__ void cp_async16(uint32_t dst, const void* src) {
    asm volatile("cp.async.cg.shared.global [%0], [%1], 16;" ::"r"(dst), "l"(src) : "memory");
}
__device__ __forceinline__ void cp_async_wait_all() { asm volatile("cp.async.wait_all;" ::: "memory"); }

__device__ __forceinline__ uint2 ld_vol2(const uint2* p) {
    uint2 v;
    asm volatile("ld.relaxed.gpu.global.v2.u32 {%0,%1}, [%2];" : "=r"(v.x), "=r"(v.y) : "l"(p) : "memory");
    return v;
}
__device__ __forceinline__ uint4 ld_vol4(const uint4* p) {
    uint4 v;
    asm volatile("ld.relaxed.gpu.global.v4.u32 {%0,%1,%2,%3}, [%4];"
                 : "=r"(v.x), "=r"(v.y), "=r"(v.z), "=r"(v.w)
                 : "l"(p)
                 : "memory");
    return v;
}
__device__ __forceinline__ void st_vol2(uint2* p, uint2 v) {
    asm volatile("st.relaxed.gpu.global.v2.u32 [%0], {%1,%2};" ::"l"(p), "r"(v.x), "r"(v.y) : "memory");
}
__device__ __forceinline__ void st_vol4(uint4* p, uint4 v) {
    asm volatile("st.relaxed.gpu.global.v4.u32 [%0], {%1,%2,%3,%4};" ::"l"(p), "r"(v.x), "r"(v.y), "r"(v.z), "r"(v.w)
                 : "memory");
}

template<int N> struct WG;
template<> struct WG<128> {
  static __device__ __forceinline__ void mma(float* d, uint64_t da, uint64_t db, int scaleD) {
    asm volatile("{\n .reg .pred p;\n setp.ne.b32 p, %66, 0;\n"
      "wgmma.mma_async.sync.aligned.m64n128k16.f32.bf16.bf16 {%0, %1, %2, %3, %4, %5, %6, %7, %8, %9, %10, %11, %12, %13, %14, %15, %16, %17, %18, %19, %20, %21, %22, %23, %24, %25, %26, %27, %28, %29, %30, %31, %32, %33, %34, %35, %36, %37, %38, %39, %40, %41, %42, %43, %44, %45, %46, %47, %48, %49, %50, %51, %52, %53, %54, %55, %56, %57, %58, %59, %60, %61, %62, %63}, %64, %65, p, 1, 1, 0, 1;\n}\n"
      : "+f"(d[0]), "+f"(d[1]), "+f"(d[2]), "+f"(d[3]), "+f"(d[4]), "+f"(d[5]), "+f"(d[6]), "+f"(d[7]), "+f"(d[8]), "+f"(d[9]), "+f"(d[10]), "+f"(d[11]), "+f"(d[12]), "+f"(d[13]), "+f"(d[14]), "+f"(d[15]), "+f"(d[16]), "+f"(d[17]), "+f"(d[18]), "+f"(d[19]), "+f"(d[20]), "+f"(d[21]), "+f"(d[22]), "+f"(d[23]), "+f"(d[24]), "+f"(d[25]), "+f"(d[26]), "+f"(d[27]), "+f"(d[28]), "+f"(d[29]), "+f"(d[30]), "+f"(d[31]), "+f"(d[32]), "+f"(d[33]), "+f"(d[34]), "+f"(d[35]), "+f"(d[36]), "+f"(d[37]), "+f"(d[38]), "+f"(d[39]), "+f"(d[40]), "+f"(d[41]), "+f"(d[42]), "+f"(d[43]), "+f"(d[44]), "+f"(d[45]), "+f"(d[46]), "+f"(d[47]), "+f"(d[48]), "+f"(d[49]), "+f"(d[50]), "+f"(d[51]), "+f"(d[52]), "+f"(d[53]), "+f"(d[54]), "+f"(d[55]), "+f"(d[56]), "+f"(d[57]), "+f"(d[58]), "+f"(d[59]), "+f"(d[60]), "+f"(d[61]), "+f"(d[62]), "+f"(d[63])
      : "l"(da), "l"(db), "r"(scaleD));
  }
};

template<> struct WG<256> {
  static __device__ __forceinline__ void mma(float* d, uint64_t da, uint64_t db, int scaleD) {
    asm volatile("{\n .reg .pred p;\n setp.ne.b32 p, %130, 0;\n"
      "wgmma.mma_async.sync.aligned.m64n256k16.f32.bf16.bf16 {%0, %1, %2, %3, %4, %5, %6, %7, %8, %9, %10, %11, %12, %13, %14, %15, %16, %17, %18, %19, %20, %21, %22, %23, %24, %25, %26, %27, %28, %29, %30, %31, %32, %33, %34, %35, %36, %37, %38, %39, %40, %41, %42, %43, %44, %45, %46, %47, %48, %49, %50, %51, %52, %53, %54, %55, %56, %57, %58, %59, %60, %61, %62, %63, %64, %65, %66, %67, %68, %69, %70, %71, %72, %73, %74, %75, %76, %77, %78, %79, %80, %81, %82, %83, %84, %85, %86, %87, %88, %89, %90, %91, %92, %93, %94, %95, %96, %97, %98, %99, %100, %101, %102, %103, %104, %105, %106, %107, %108, %109, %110, %111, %112, %113, %114, %115, %116, %117, %118, %119, %120, %121, %122, %123, %124, %125, %126, %127}, %128, %129, p, 1, 1, 0, 1;\n}\n"
      : "+f"(d[0]), "+f"(d[1]), "+f"(d[2]), "+f"(d[3]), "+f"(d[4]), "+f"(d[5]), "+f"(d[6]), "+f"(d[7]), "+f"(d[8]), "+f"(d[9]), "+f"(d[10]), "+f"(d[11]), "+f"(d[12]), "+f"(d[13]), "+f"(d[14]), "+f"(d[15]), "+f"(d[16]), "+f"(d[17]), "+f"(d[18]), "+f"(d[19]), "+f"(d[20]), "+f"(d[21]), "+f"(d[22]), "+f"(d[23]), "+f"(d[24]), "+f"(d[25]), "+f"(d[26]), "+f"(d[27]), "+f"(d[28]), "+f"(d[29]), "+f"(d[30]), "+f"(d[31]), "+f"(d[32]), "+f"(d[33]), "+f"(d[34]), "+f"(d[35]), "+f"(d[36]), "+f"(d[37]), "+f"(d[38]), "+f"(d[39]), "+f"(d[40]), "+f"(d[41]), "+f"(d[42]), "+f"(d[43]), "+f"(d[44]), "+f"(d[45]), "+f"(d[46]), "+f"(d[47]), "+f"(d[48]), "+f"(d[49]), "+f"(d[50]), "+f"(d[51]), "+f"(d[52]), "+f"(d[53]), "+f"(d[54]), "+f"(d[55]), "+f"(d[56]), "+f"(d[57]), "+f"(d[58]), "+f"(d[59]), "+f"(d[60]), "+f"(d[61]), "+f"(d[62]), "+f"(d[63]), "+f"(d[64]), "+f"(d[65]), "+f"(d[66]), "+f"(d[67]), "+f"(d[68]), "+f"(d[69]), "+f"(d[70]), "+f"(d[71]), "+f"(d[72]), "+f"(d[73]), "+f"(d[74]), "+f"(d[75]), "+f"(d[76]), "+f"(d[77]), "+f"(d[78]), "+f"(d[79]), "+f"(d[80]), "+f"(d[81]), "+f"(d[82]), "+f"(d[83]), "+f"(d[84]), "+f"(d[85]), "+f"(d[86]), "+f"(d[87]), "+f"(d[88]), "+f"(d[89]), "+f"(d[90]), "+f"(d[91]), "+f"(d[92]), "+f"(d[93]), "+f"(d[94]), "+f"(d[95]), "+f"(d[96]), "+f"(d[97]), "+f"(d[98]), "+f"(d[99]), "+f"(d[100]), "+f"(d[101]), "+f"(d[102]), "+f"(d[103]), "+f"(d[104]), "+f"(d[105]), "+f"(d[106]), "+f"(d[107]), "+f"(d[108]), "+f"(d[109]), "+f"(d[110]), "+f"(d[111]), "+f"(d[112]), "+f"(d[113]), "+f"(d[114]), "+f"(d[115]), "+f"(d[116]), "+f"(d[117]), "+f"(d[118]), "+f"(d[119]), "+f"(d[120]), "+f"(d[121]), "+f"(d[122]), "+f"(d[123]), "+f"(d[124]), "+f"(d[125]), "+f"(d[126]), "+f"(d[127])
      : "l"(da), "l"(db), "r"(scaleD));
  }
};

constexpr int POLL_LIMIT = 1 << 22;
__device__ __forceinline__ void wait_counter(const unsigned* cnt, unsigned target, int err) {
    int it = 0;
    unsigned v;
    do {
        asm volatile("ld.acquire.gpu.global.u32 %0, [%1];" : "=r"(v) : "l"(cnt) : "memory");
        if (v >= target) break;
        __nanosleep(64);
    } while (++it < POLL_LIMIT);
    if (v < target) g_err = err;
}
__device__ __forceinline__ void signal_counter(unsigned* cnt) {
    __threadfence();
    asm volatile("red.relaxed.gpu.global.add.u32 [%0], 1;" ::"l"(cnt) : "memory");
}

template <int NCOL>
__device__ __forceinline__ void ln_row(const bf16* __restrict__ src, bf16* __restrict__ dst, int lane) {
    constexpr int PER = (NCOL + 31) / 32;
    float v[PER];
    float sum = 0.f;
#pragma unroll
    for (int i = 0; i < PER; ++i) {
        int c = lane + 32 * i;
        v[i] = (c < NCOL) ? __bfloat162float(src[c]) : 0.f;
        sum += v[i];
    }
#pragma unroll
    for (int o = 16; o; o >>= 1) sum += __shfl_xor_sync(0xffffffffu, sum, o);
    float mean = sum / (float)NCOL;
    float sq = 0.f;
#pragma unroll
    for (int i = 0; i < PER; ++i) {
        int c = lane + 32 * i;
        float d = v[i] - mean;
        if (c < NCOL) sq += d * d;
    }
#pragma unroll
    for (int o = 16; o; o >>= 1) sq += __shfl_xor_sync(0xffffffffu, sq, o);
    float mb = bf16r(mean);
    float vb = bf16r(sq / (float)NCOL);
    float den = bf16r(sqrtf(bf16r(vb + 1e-5f)));
#pragma unroll
    for (int i = 0; i < PER; ++i) {
        int c = lane + 32 * i;
        if (c < NCOL) dst[c] = __float2bfloat16_rn(bf16r(v[i] - mb) / den);
    }
}

__global__ void __launch_bounds__(256) ln1_kernel(const bf16* __restrict__ x) {
    int warp = threadIdx.x >> 5, lane = threadIdx.x & 31;
    int row = blockIdx.x * 8 + warp;
    ln_row<D_>(x + (size_t)row * D_, g_xn + (size_t)row * D_, lane);
    float4* a = reinterpret_cast<float4*>(g_acc) + blockIdx.x * 320;
    for (int i = threadIdx.x; i < 320; i += 256) a[i] = make_float4(0.f, 0.f, 0.f, 0.f);
    if (blockIdx.x == 0) for (int i = threadIdx.x; i < (NSEG_ + 1) * 32; i += 256) g_cnt[i] = 0u;
    if (blockIdx.x == 1) for (int i = threadIdx.x; i < 32 * 32; i += 256) { g_kvflag[i] = 0u; g_atflag[i] = 0u; }
}
__global__ void __launch_bounds__(256) ln2_kernel() {
    int warp = threadIdx.x >> 5, lane = threadIdx.x & 31;
    int row = blockIdx.x * 8 + warp;
    ln_row<FH_>(g_z + (size_t)row * F_ + FH_, g_z2n + (size_t)row * FH_, lane);
}

enum { EPI_STORE = 0, EPI_GELU = 1, EPI_GATE = 2, EPI_SILU = 3, EPI_FINAL = 4 };

struct EpiArgs {
    bf16* out;
    int ldo;
    const bf16* aux1;
    int ld1;
    const bf16* aux2;
    int ld2;
    const bf16* bias;
    int nvalid;
    const unsigned* wait_flag;
    unsigned wait_target;
    unsigned* done_flag;
};
struct TMaps3 {
    CUtensorMap m[3];
};
struct Out3 {
    bf16* p[3];
};

__device__ __forceinline__ float gelu_tanh(float x) {
    float u = 0.7978845608028654f * (x + 0.044715f * x * x * x);
    return 0.5f * x * (1.f + tanhf(u));
}

template <int NWG, int BN, int STAGES, int EPI>
__device__ __forceinline__ void gemm_body(const CUtensorMap* tmA, const CUtensorMap* tmB, const EpiArgs& ea, int K,
                                          int m0, int n0) {
    constexpr int A_BYTES = NWG * 64 * 64 * 2, B_BYTES = BN * 64 * 2, STAGE_BYTES = A_BYTES + B_BYTES;
    extern __shared__ uint8_t smem_raw[];
    uint32_t sbase = (smem_u32(smem_raw) + 1023) & ~1023u;
    uint8_t* sgen = smem_raw + (sbase - smem_u32(smem_raw));
    uint32_t bar0 = sbase + STAGES * STAGE_BYTES;
    const int warp = threadIdx.x >> 5, lane = threadIdx.x & 31;
    if (threadIdx.x == 0) {
        for (int i = 0; i < STAGES; ++i) {
            mbar_init(bar0 + 8 * i, 1);
            mbar_init(bar0 + 8 * (STAGES + i), 4 * NWG);
        }
        asm volatile("fence.mbarrier_init.release.cluster;" ::: "memory");
    }
    if (ea.wait_flag && threadIdx.x == (NWG == 2 ? 256 : 0)) wait_counter(ea.wait_flag + (m0 / 64) * 32, ea.wait_target, 10);
    __syncthreads();
    const int nk = K / 64;
    auto issue = [&](int kt) {
        int st = kt % STAGES;
        uint32_t fb = bar0 + 8 * st;
        mbar_expect_tx(fb, STAGE_BYTES);
        uint32_t sa = sbase + st * STAGE_BYTES;
        tma_load_2d(sa, tmA, kt * 64, m0, fb);
#pragma unroll
        for (int j = 0; j < BN / 64; ++j) tma_load_2d(sa + A_BYTES + j * 8192, tmB, n0 + j * 64, kt * 64, fb);
    };
    if (NWG == 2) {
        if (warp == 4 * NWG) {
            if (lane == 0) {
                for (int kt = 0; kt < nk; ++kt) {
                    if (kt >= STAGES) mbar_wait(bar0 + 8 * (STAGES + kt % STAGES), ((kt / STAGES) - 1) & 1);
                    issue(kt);
                }
            }
            return;
        }
    } else {
        if (threadIdx.x == 0)
            for (int kt = 0; kt < STAGES && kt < nk; ++kt) issue(kt);
    }
    const int wg = warp >> 2;
    float acc[BN / 2];
#pragma unroll
    for (int i = 0; i < BN / 2; ++i) acc[i] = 0.f;
    for (int kt = 0; kt < nk; ++kt) {
        int st = kt % STAGES;
        mbar_wait(bar0 + 8 * st, (kt / STAGES) & 1);
        uint32_t sa = sbase + st * STAGE_BYTES;
        uint64_t da = make_desc(sa + wg * 8192, 16, 1024);
        uint64_t db = make_desc(sa + A_BYTES, 8192, 1024);
        wgmma_fence();
#pragma unroll
        for (int kk = 0; kk < 4; ++kk) WG<BN>::mma(acc, da + kk * 2, db + kk * 128, 1);
        wgmma_commit();
        wgmma_wait<1>();
        if (kt > 0 && lane == 0) mbar_arrive(bar0 + 8 * (STAGES + (kt - 1) % STAGES));
        if (NWG == 1 && threadIdx.x == 0 && kt > 0 && kt - 1 + STAGES < nk) {
            mbar_wait(bar0 + 8 * (STAGES + (kt - 1) % STAGES), ((kt - 1) / STAGES) & 1);
            issue(kt - 1 + STAGES);
        }
    }
    wgmma_wait<0>();
    named_bar(1, 128 * NWG);
    constexpr int LDS_ = BN * 2 + 16;
    uint8_t* stg = sgen + wg * (64 * LDS_);
    {
        int r0 = (warp & 3) * 16 + (lane >> 2);
#pragma unroll
        for (int i = 0; i < BN / 8; ++i) {
            int c = i * 8 + (lane & 3) * 2;
            *reinterpret_cast<uint32_t*>(stg + r0 * LDS_ + c * 2) = pack_bf16(acc[4 * i], acc[4 * i + 1]);
            *reinterpret_cast<uint32_t*>(stg + (r0 + 8) * LDS_ + c * 2) = pack_bf16(acc[4 * i + 2], acc[4 * i + 3]);
        }
    }
    named_bar(2 + wg, 128);
    {
        constexpr int CH = BN / 8;
        constexpr int RPI = 128 / CH;
        int t = threadIdx.x & 127;
        int ch = t % CH, rr = t / CH;
#pragma unroll
        for (int it = 0; it < 64 / RPI; ++it) {
            int r = rr + it * RPI;
            int grow = m0 + wg * 64 + r;
            int gcol = n0 + ch * 8;
            if (gcol >= ea.nvalid) continue;
            uint4 raw = *reinterpret_cast<const uint4*>(stg + r * LDS_ + ch * 16);
            if (EPI != EPI_STORE) {
                __nv_bfloat162* vv = reinterpret_cast<__nv_bfloat162*>(&raw);
                if (EPI == EPI_GELU) {
#pragma unroll
                    for (int e = 0; e < 4; ++e) {
                        float2 f = __bfloat1622float2(vv[e]);
                        vv[e] = __floats2bfloat162_rn(gelu_tanh(f.x), gelu_tanh(f.y));
                    }
                } else if (EPI == EPI_GATE) {
                    float b = __bfloat162float(ea.bias[grow]);
                    uint4 z1 = *reinterpret_cast<const uint4*>(ea.aux1 + (size_t)grow * ea.ld1 + gcol);
                    __nv_bfloat162* zz = reinterpret_cast<__nv_bfloat162*>(&z1);
#pragma unroll
                    for (int e = 0; e < 4; ++e) {
                        float2 f = __bfloat1622float2(vv[e]);
                        float2 z = __bfloat1622float2(zz[e]);
                        vv[e] = __floats2bfloat162_rn(z.x * bf16r(f.x + b), z.y * bf16r(f.y + b));
                    }
                } else if (EPI == EPI_SILU) {
#pragma unroll
                    for (int e = 0; e < 4; ++e) {
                        float2 f = __bfloat1622float2(vv[e]);
                        vv[e] = __floats2bfloat162_rn(f.x / (1.f + __expf(-f.x)), f.y / (1.f + __expf(-f.y)));
                    }
                } else if (EPI == EPI_FINAL) {
                    uint4 gg = *reinterpret_cast<const uint4*>(ea.aux1 + (size_t)grow * ea.ld1 + gcol);
                    uint4 xx = *reinterpret_cast<const uint4*>(ea.aux2 + (size_t)grow * ea.ld2 + gcol);
                    __nv_bfloat162* g2 = reinterpret_cast<__nv_bfloat162*>(&gg);
                    __nv_bfloat162* x2 = reinterpret_cast<__nv_bfloat162*>(&xx);
#pragma unroll
                    for (int e = 0; e < 4; ++e) {
                        float2 f = __bfloat1622float2(vv[e]);
                        float2 g = __bfloat1622float2(g2[e]);
                        float2 x = __bfloat1622float2(x2[e]);
                        vv[e] = __floats2bfloat162_rn(x.x + bf16r(f.x * g.x), x.y + bf16r(f.y * g.y));
                    }
                }
            }
            *reinterpret_cast<uint4*>(ea.out + (size_t)grow * ea.ldo + gcol) = raw;
        }
    }
    if (ea.done_flag) {
        named_bar(1, 128 * NWG);
        if (threadIdx.x == 0) signal_counter(ea.done_flag + (m0 / 64) * 32);
    }
}

template <int NWG, int BN, int STAGES, int EPI>
__global__ void __launch_bounds__(NWG == 2 ? 288 : 128) gemm_kernel(const __grid_constant__ CUtensorMap tmA,
                                                              const __grid_constant__ CUtensorMap tmB, EpiArgs ea, int K) {
    gemm_body<NWG, BN, STAGES, EPI>(&tmA, &tmB, ea, K, blockIdx.y * 64 * NWG, blockIdx.x * BN);
}

template <int NWG, int BN, int STAGES>
__global__ void __launch_bounds__(NWG == 2 ? 288 : 128) gemm_qkv_kernel(const __grid_constant__ CUtensorMap tmA,
                                                                       const __grid_constant__ TMaps3 tmB, Out3 outs, int K,
                                                                       int z0, unsigned* done_flag) {
    constexpr int NT = HD_ / BN;
    const int z = z0 + blockIdx.x / NT, nt = blockIdx.x % NT;
    EpiArgs ea;
    ea.out = outs.p[z];
    ea.ldo = HD_;
    ea.aux1 = nullptr; ea.ld1 = 0; ea.aux2 = nullptr; ea.ld2 = 0; ea.bias = nullptr;
    ea.nvalid = HD_;
    ea.wait_flag = nullptr; ea.wait_target = 0; ea.done_flag = done_flag;
    gemm_body<NWG, BN, STAGES, EPI_STORE>(&tmA, &tmB.m[z], ea, K, blockIdx.y * 64 * NWG, nt * BN);
}

constexpr int CH_T = 320;
constexpr int CH_MEM_LD = 648;
constexpr int CH_K_LD = 40;
constexpr int CH_V_LD = 136;
constexpr int CH_P_LD = 56;
constexpr int OFF_MEM = 0;
constexpr int OFF_RED = OFF_MEM + 8 * CH_MEM_LD * 2;
constexpr int OFF_Q = OFF_RED + 5 * 96 * 8 * 4;
constexpr int OFF_KEYS = OFF_Q + 8 * CH_K_LD * 2;
constexpr int OFF_VALS = OFF_KEYS + 2 * 48 * CH_K_LD * 2;
constexpr int OFF_P = OFF_VALS + 2 * 48 * CH_V_LD * 2;
constexpr int OFF_O = OFF_P + 8 * CH_P_LD * 2;
constexpr int OFF_WO = OFF_O + 8 * CH_V_LD * 2;
constexpr int OFF_WV = OFF_WO + 128 * 168 * 2;
constexpr int OFF_END = OFF_WV + 640 * 40 * 2;
constexpr int OFF_STAGE = 0;
constexpr int CH_STAGE_BYTES = 640 * 72 * 2;
constexpr int CH_SMEM = OFF_END > CH_STAGE_BYTES ? OFF_END : CH_STAGE_BYTES;

#define PROF(i)

__global__ void __maxnreg__(128) chain_kernel(const bf16* __restrict__ Wq, const bf16* __restrict__ Wk,
                                                        const bf16* __restrict__ Wv, const bf16* __restrict__ Wo,
                                                        const bf16* __restrict__ mem0) {
    extern __shared__ __align__(16) uint8_t sm[];
    const int tid = threadIdx.x, warp = tid >> 5, lane = tid & 31;
    const int g = lane >> 2, t4 = lane & 3;
    const int cta = blockIdx.x, h = cta >> 2, j = cta & 3;
    const int colbase = h * DH_ + j * 32;
    bf16* mem = reinterpret_cast<bf16*>(sm + OFF_MEM);
    float* red = reinterpret_cast<float*>(sm + OFF_RED);
    bf16* q_s = reinterpret_cast<bf16*>(sm + OFF_Q);
    bf16* keys = reinterpret_cast<bf16*>(sm + OFF_KEYS);
    bf16* vals = reinterpret_cast<bf16*>(sm + OFF_VALS);
    bf16* p_s = reinterpret_cast<bf16*>(sm + OFF_P);
    bf16* o_s = reinterpret_cast<bf16*>(sm + OFF_O);
    bf16* stage = reinterpret_cast<bf16*>(sm + OFF_STAGE);
    bf16* wo_s = reinterpret_cast<bf16*>(sm + OFF_WO);
    bf16* wv_s = reinterpret_cast<bf16*>(sm + OFF_WV);

    uint32_t wa[2][8][4];
    const int kg = warp % 5, mh = warp / 5;

    for (int i = tid; i < 640 * 8; i += CH_T) {
        int k = i / 8, r = i % 8, mat = r >> 2, ch = r & 3;
        const bf16* W = mat == 0 ? Wq : Wk;
        *reinterpret_cast<uint4*>(stage + k * 72 + mat * 32 + ch * 8) =
            *reinterpret_cast<const uint4*>(W + (size_t)k * HD_ + colbase + ch * 8);
    }
    __syncthreads();
    {
        uint32_t sa = smem_u32(stage);
#pragma unroll
        for (int mi = 0; mi < 2; ++mi)
#pragma unroll
            for (int ks = 0; ks < 8; ++ks) {
                int krow = kg * 128 + ks * 16 + (lane & 7) + ((lane >> 4) << 3);
                int mcol = (mh * 2 + mi) * 16 + ((lane >> 3) & 1) * 8;
                ldsm_x4_t(wa[mi][ks][0], wa[mi][ks][1], wa[mi][ks][2], wa[mi][ks][3], sa + (krow * 72 + mcol) * 2);
            }
    }
    __syncthreads();
    for (int i = tid; i < 640 * 4; i += CH_T) {
        int k = i >> 2, ch = i & 3;
        *reinterpret_cast<uint4*>(wv_s + k * 40 + ch * 8) = *reinterpret_cast<const uint4*>(Wv + (size_t)k * HD_ + colbase + ch * 8);
    }
    for (int i = tid; i < 128 * 20; i += CH_T) {
        int k = i / 20, ch = i % 20;
        *reinterpret_cast<uint4*>(wo_s + k * 168 + ch * 8) =
            *reinterpret_cast<const uint4*>(Wo + (size_t)(h * DH_ + k) * D_ + j * 160 + ch * 8);
    }
    for (int i = tid; i < 8 * 80; i += CH_T) {
        int n = i / 80, ch = i % 80;
        *reinterpret_cast<uint4*>(mem + n * CH_MEM_LD + ch * 8) = *reinterpret_cast<const uint4*>(mem0 + n * D_ + ch * 8);
    }
    for (int i = tid; i < 2 * 8 * CH_K_LD; i += CH_T) {
        int b = i / (8 * CH_K_LD), r = i % (8 * CH_K_LD);
        keys[b * 48 * CH_K_LD + 40 * CH_K_LD + r] = __float2bfloat16_rn(0.f);
    }
    for (int i = tid; i < 2 * 8 * CH_V_LD; i += CH_T) {
        int b = i / (8 * CH_V_LD), r = i % (8 * CH_V_LD);
        vals[b * 48 * CH_V_LD + 40 * CH_V_LD + r] = __float2bfloat16_rn(0.f);
    }
    for (int i = tid; i < 8 * CH_P_LD; i += CH_T) p_s[i] = __float2bfloat16_rn(0.f);

    auto prefetch = [&](int seg, int b, bool first) {
        bf16* kb = keys + b * 48 * CH_K_LD;
        bf16* vb = vals + b * 48 * CH_V_LD;
        for (int i = (first ? tid : tid - 32); i < 32 * 4 + 32 * 16; i += (first ? CH_T : CH_T - 32)) {
            if (i < 128) {
                int r = i >> 2, ch = i & 3;
                cp_async16(smem_u32(kb + (8 + r) * CH_K_LD + ch * 8), g_k + (size_t)(seg * SEG_ + r) * HD_ + colbase + ch * 8);
            } else {
                int ii = i - 128, r = ii >> 4, ch = ii & 15;
                cp_async16(smem_u32(vb + (8 + r) * CH_V_LD + ch * 8), g_v + (size_t)(seg * SEG_ + r) * HD_ + h * DH_ + ch * 8);
            }
        }
    };
    prefetch(0, 0, true);
    __syncthreads();

    const uint32_t mem_a = smem_u32(mem);
    const float scale = 0.08838834764831845f;

    for (int s = 0; s < NSEG_; ++s) {
        const int buf = s & 1;
        const uint32_t tag = s + 1;
        bf16* keys_b = keys + buf * 48 * CH_K_LD;
        bf16* vals_b = vals + buf * 48 * CH_V_LD;
        PROF(8);
        {
            uint32_t b[8][2];
#pragma unroll
            for (int i = 0; i < 4; ++i)
                ldsm_x4(b[2 * i][0], b[2 * i][1], b[2 * i + 1][0], b[2 * i + 1][1],
                        mem_a + ((lane & 7) * CH_MEM_LD + kg * 128 + i * 32 + (lane >> 3) * 8) * 2);
            float acc[3][4];
#pragma unroll
            for (int mi = 0; mi < 3; ++mi)
#pragma unroll
                for (int e = 0; e < 4; ++e) acc[mi][e] = 0.f;
            uint32_t va = smem_u32(wv_s) + ((kg * 128 + (lane & 7) + ((lane >> 4) << 3)) * 40 + mh * 16 + ((lane >> 3) & 1) * 8) * 2;
#pragma unroll
            for (int ks = 0; ks < 8; ++ks) {
                uint32_t a0, a1, a2, a3;
                ldsm_x4_t(a0, a1, a2, a3, va + ks * 16 * 40 * 2);
                mma16816(acc[0], wa[0][ks][0], wa[0][ks][1], wa[0][ks][2], wa[0][ks][3], b[ks][0], b[ks][1]);
                mma16816(acc[1], wa[1][ks][0], wa[1][ks][1], wa[1][ks][2], wa[1][ks][3], b[ks][0], b[ks][1]);
                mma16816(acc[2], a0, a1, a2, a3, b[ks][0], b[ks][1]);
            }
            float* rw = red + kg * 768;
#pragma unroll
            for (int mi = 0; mi < 3; ++mi) {
                int m = (mi < 2 ? (mh * 2 + mi) : (4 + mh)) * 16 + g;
                *reinterpret_cast<float2*>(rw + m * 8 + t4 * 2) = make_float2(acc[mi][0], acc[mi][1]);
                *reinterpret_cast<float2*>(rw + (m + 8) * 8 + t4 * 2) = make_float2(acc[mi][2], acc[mi][3]);
            }
        }
        PROF(10);
        __syncthreads();
        PROF(0);
        uint2* vx_mine = g_vx + ((buf * H_ + h) * 4 + j) * 128;
#pragma unroll
        for (int rnd = 0; rnd < 2; ++rnd) {
            int pi = tid + rnd * CH_T;
            if (pi < 384) {
                int m = (pi >> 3) * 2, n = pi & 7;
                float v0 = 0.f, v1 = 0.f;
#pragma unroll
                for (int w = 0; w < 5; ++w) {
                    v0 += red[w * 768 + m * 8 + n];
                    v1 += red[w * 768 + m * 8 + 8 + n];
                }
                uint32_t pk = pack_bf16(v0, v1);
                int which = m >> 5, e = m & 31;
                if (which == 0) {
                    *reinterpret_cast<uint32_t*>(q_s + n * CH_K_LD + e) = pk;
                } else if (which == 1) {
                    *reinterpret_cast<uint32_t*>(keys_b + n * CH_K_LD + e) = pk;
                    *reinterpret_cast<uint32_t*>(g_km + (size_t)(s * MM_ + n) * HD_ + colbase + e) = pk;
                } else {
                    *reinterpret_cast<uint32_t*>(vals_b + n * CH_V_LD + j * 32 + e) = pk;
                    *reinterpret_cast<uint32_t*>(g_vm + (size_t)(s * MM_ + n) * HD_ + colbase + e) = pk;
                    if (s + 1 < NSEG_) st_vol2(vx_mine + n * 16 + (e >> 1), make_uint2(pk, tag));
                }
            }
        }
        if (s == NSEG_ - 1) {
            __syncthreads();
            if (tid == 0) signal_counter(g_cnt + NSEG_ * 32);
            break;
        }
        cp_async_wait_all();
        __syncthreads();
        PROF(1);
        if (warp < 3) {
            uint2* sx_mine = g_sx + ((buf * H_ + h) * 4 + j) * 320;
            float c[4] = {0.f, 0.f, 0.f, 0.f};
            uint32_t a0, a1, a2, a3, b0, b1, b2, b3;
            uint32_t kb = smem_u32(keys_b), qb = smem_u32(q_s);
            ldsm_x4(b0, b1, b2, b3, qb + ((lane & 7) * CH_K_LD + (lane >> 3) * 8) * 2);
#pragma unroll
            for (int ks = 0; ks < 2; ++ks) {
                int row = warp * 16 + (lane & 7) + ((lane >> 3) & 1) * 8;
                int col = ks * 16 + (lane >> 4) * 8;
                ldsm_x4(a0, a1, a2, a3, kb + (row * CH_K_LD + col) * 2);
                mma16816(c, a0, a1, a2, a3, ks ? b2 : b0, ks ? b3 : b1);
            }
            int key = warp * 16 + g, n = t4 * 2;
            st_vol2(sx_mine + n * 40 + key, make_uint2(__float_as_uint(c[0]), tag));
            st_vol2(sx_mine + (n + 1) * 40 + key, make_uint2(__float_as_uint(c[1]), tag));
            if (key + 8 < 40) {
                st_vol2(sx_mine + n * 40 + key + 8, make_uint2(__float_as_uint(c[2]), tag));
                st_vol2(sx_mine + (n + 1) * 40 + key + 8, make_uint2(__float_as_uint(c[3]), tag));
            }
        }
        PROF(2);
        if (warp < 8) {
            const int n = warp;
            float sc[2];
            uint2 v[2][4];
            const uint2* src0 = g_sx + ((buf * H_ + h) * 4) * 320 + n * 40 + lane;
            const bool two = (lane + 32 < 40);
            int it = 0;
            while (true) {
#pragma unroll
                for (int jj = 0; jj < 4; ++jj) v[0][jj] = ld_vol2(src0 + jj * 320);
                if (two) {
#pragma unroll
                    for (int jj = 0; jj < 4; ++jj) v[1][jj] = ld_vol2(src0 + jj * 320 + 32);
                }
                bool ok = true;
#pragma unroll
                for (int jj = 0; jj < 4; ++jj) ok = ok && (v[0][jj].y == tag) && (!two || v[1][jj].y == tag);
                if (ok) break;
                if (++it > POLL_LIMIT) { g_err = 1; break; }
            }
            float t0 = (__uint_as_float(v[0][0].x) + __uint_as_float(v[0][1].x)) + (__uint_as_float(v[0][2].x) + __uint_as_float(v[0][3].x));
            sc[0] = bf16r(bf16r(t0) * scale);
            sc[1] = -INFINITY;
            if (two) {
                float t1 = (__uint_as_float(v[1][0].x) + __uint_as_float(v[1][1].x)) + (__uint_as_float(v[1][2].x) + __uint_as_float(v[1][3].x));
                sc[1] = bf16r(bf16r(t1) * scale);
            }
            float mx = fmaxf(sc[0], sc[1]);
#pragma unroll
            for (int o = 16; o; o >>= 1) mx = fmaxf(mx, __shfl_xor_sync(0xffffffffu, mx, o));
            float e0 = __expf(sc[0] - mx), e1 = two ? __expf(sc[1] - mx) : 0.f;
            float sum = e0 + e1;
#pragma unroll
            for (int o = 16; o; o >>= 1) sum += __shfl_xor_sync(0xffffffffu, sum, o);
            float inv = 1.f / sum;
            p_s[n * CH_P_LD + lane] = __float2bfloat16_rn(e0 * inv);
            if (two) p_s[n * CH_P_LD + lane + 32] = __float2bfloat16_rn(e1 * inv);
        } else {
            int u = tid - 256;
            uint2 v[6];
            int it = 0;
            while (true) {
#pragma unroll
                for (int i = 0; i < 6; ++i) {
                    int id = u + 64 * i;
                    int jo = id >> 7;
                    int jj = jo + (jo >= j ? 1 : 0);
                    v[i] = ld_vol2(g_vx + ((buf * H_ + h) * 4 + jj) * 128 + (id & 127));
                }
                bool ok = true;
#pragma unroll
                for (int i = 0; i < 6; ++i) ok = ok && (v[i].y == tag);
                if (ok) break;
                if (++it > POLL_LIMIT) { g_err = 4; break; }
            }
#pragma unroll
            for (int i = 0; i < 6; ++i) {
                int id = u + 64 * i;
                int jo = id >> 7;
                int jj = jo + (jo >= j ? 1 : 0);
                int n = (id & 127) >> 4, ep = id & 15;
                *reinterpret_cast<uint32_t*>(vals_b + n * CH_V_LD + jj * 32 + ep * 2) = v[i].x;
            }
        }
        __syncthreads();
        PROF(3);
        if (warp < 8) {
            float c[4] = {0.f, 0.f, 0.f, 0.f};
            uint32_t vb = smem_u32(vals_b), pb = smem_u32(p_s);
            uint32_t b0, b1, b2, b3, b4, b5;
            ldsm_x4(b0, b1, b2, b3, pb + ((lane & 7) * CH_P_LD + (lane >> 3) * 8) * 2);
            ldsm_x2(b4, b5, pb + ((lane & 7) * CH_P_LD + 32 + ((lane >> 3) & 1) * 8) * 2);
#pragma unroll
            for (int ks = 0; ks < 3; ++ks) {
                uint32_t a0, a1, a2, a3;
                int krow = ks * 16 + (lane & 7) + ((lane >> 4) << 3);
                int mcol = warp * 16 + ((lane >> 3) & 1) * 8;
                ldsm_x4_t(a0, a1, a2, a3, vb + (krow * CH_V_LD + mcol) * 2);
                mma16816(c, a0, a1, a2, a3, ks == 0 ? b0 : (ks == 1 ? b2 : b4), ks == 0 ? b1 : (ks == 1 ? b3 : b5));
            }
            int e = warp * 16 + g, n = t4 * 2;
            o_s[n * CH_V_LD + e] = __float2bfloat16_rn(c[0]);
            o_s[(n + 1) * CH_V_LD + e] = __float2bfloat16_rn(c[1]);
            o_s[n * CH_V_LD + e + 8] = __float2bfloat16_rn(c[2]);
            o_s[(n + 1) * CH_V_LD + e + 8] = __float2bfloat16_rn(c[3]);
        }
        __syncthreads();
        PROF(4);
        {
            uint32_t ob = smem_u32(o_s);
            uint32_t b[8][2];
#pragma unroll
            for (int i = 0; i < 4; ++i)
                ldsm_x4(b[2 * i][0], b[2 * i][1], b[2 * i + 1][0], b[2 * i + 1][1], ob + ((lane & 7) * CH_V_LD + i * 32 + (lane >> 3) * 8) * 2);
            float c0[4] = {0.f, 0.f, 0.f, 0.f}, c1[4] = {0.f, 0.f, 0.f, 0.f};
            uint32_t wa_s = smem_u32(wo_s) + (((lane & 7) + ((lane >> 4) << 3)) * 168 + warp * 16 + ((lane >> 3) & 1) * 8) * 2;
#pragma unroll
            for (int ks = 0; ks < 4; ++ks) {
                uint32_t a0, a1, a2, a3, a4, a5, a6, a7;
                ldsm_x4_t(a0, a1, a2, a3, wa_s + ks * 16 * 168 * 2);
                ldsm_x4_t(a4, a5, a6, a7, wa_s + (ks + 4) * 16 * 168 * 2);
                mma16816(c0, a0, a1, a2, a3, b[ks][0], b[ks][1]);
                mma16816(c1, a4, a5, a6, a7, b[ks + 4][0], b[ks + 4][1]);
            }
            int col0 = j * 160 + warp * 16 + g;
            float* accp = g_acc + (size_t)(s + 1) * (D_ * MM_);
            asm volatile("red.relaxed.gpu.global.add.v2.f32 [%0], {%1,%2};" ::"l"(accp + col0 * 8 + t4 * 2),
                         "f"(c0[0] + c1[0]), "f"(c0[1] + c1[1]) : "memory");
            asm volatile("red.relaxed.gpu.global.add.v2.f32 [%0], {%1,%2};" ::"l"(accp + (col0 + 8) * 8 + t4 * 2),
                         "f"(c0[2] + c1[2]), "f"(c0[3] + c1[3]) : "memory");
        }
        __syncthreads();
        if (warp > 0) {
            prefetch(s + 1, buf ^ 1, false);
        }
        PROF(5);
        if (tid == 0) {
            unsigned* cnt = g_cnt + (s + 1) * 32;
            __threadfence();
            asm volatile("red.relaxed.gpu.global.add.u32 [%0], 1;" ::"l"(cnt) : "memory");
            int it = 0;
            unsigned v;
            do {
                asm volatile("ld.acquire.gpu.global.u32 %0, [%1];" : "=r"(v) : "l"(cnt) : "memory");
                if (++it > POLL_LIMIT) { g_err = 2; break; }
            } while (v < 128u);
        }
        __syncthreads();
        PROF(6);
        {
            const float4* src = reinterpret_cast<const float4*>(g_acc + (size_t)(s + 1) * (D_ * MM_));
            float4 v[4];
#pragma unroll
            for (int i = 0; i < 4; ++i) v[i] = __ldcg(src + tid + CH_T * i);
#pragma unroll
            for (int i = 0; i < 4; ++i) {
                int id = tid + CH_T * i;
                int col = id >> 1, n0 = (id & 1) * 4;
                mem[(n0 + 0) * CH_MEM_LD + col] = __float2bfloat16_rn(v[i].x);
                mem[(n0 + 1) * CH_MEM_LD + col] = __float2bfloat16_rn(v[i].y);
                mem[(n0 + 2) * CH_MEM_LD + col] = __float2bfloat16_rn(v[i].z);
                mem[(n0 + 3) * CH_MEM_LD + col] = __float2bfloat16_rn(v[i].w);
            }
        }
        __syncthreads();
        PROF(7);
    }
}

constexpr int AT_LD = 136;
__global__ void __launch_bounds__(64) attn_kernel() {
    __shared__ __align__(16) bf16 sq[32 * AT_LD];
    __shared__ __align__(16) bf16 sk[40 * AT_LD];
    __shared__ __align__(16) bf16 sv[48 * AT_LD];
    const int s = blockIdx.x >> 5, h = blockIdx.x & 31;
    const int tid = threadIdx.x, warp = tid >> 5, lane = tid & 31;
    for (int i = tid; i < 32 * 16; i += 64) {
        int r = i >> 4, ch = i & 15;
        cp_async16(smem_u32(sq + r * AT_LD + ch * 8), g_q + (size_t)(s * SEG_ + r) * HD_ + h * DH_ + ch * 8);
    }
    for (int i = tid; i < 40 * 16; i += 64) {
        int r = i >> 4, ch = i & 15;
        const bf16* ks = r < 8 ? g_km + (size_t)(s * MM_ + r) * HD_ : g_k + (size_t)(s * SEG_ + r - 8) * HD_;
        const bf16* vs = r < 8 ? g_vm + (size_t)(s * MM_ + r) * HD_ : g_v + (size_t)(s * SEG_ + r - 8) * HD_;
        cp_async16(smem_u32(sk + r * AT_LD + ch * 8), ks + h * DH_ + ch * 8);
        cp_async16(smem_u32(sv + r * AT_LD + ch * 8), vs + h * DH_ + ch * 8);
    }
    for (int i = tid; i < 8 * 16; i += 64) {
        int r = 40 + (i >> 4), ch = i & 15;
        *reinterpret_cast<uint4*>(sv + r * AT_LD + ch * 8) = make_uint4(0, 0, 0, 0);
    }
    cp_async_wait_all();
    __syncthreads();
    float sc[5][4];
#pragma unroll
    for (int n = 0; n < 5; ++n)
#pragma unroll
        for (int e = 0; e < 4; ++e) sc[n][e] = 0.f;
    uint32_t qa = smem_u32(sq), ka = smem_u32(sk), va = smem_u32(sv);
#pragma unroll
    for (int ks = 0; ks < 8; ++ks) {
        uint32_t a0, a1, a2, a3;
        int row = warp * 16 + (lane & 7) + ((lane >> 3) & 1) * 8;
        ldsm_x4(a0, a1, a2, a3, qa + (row * AT_LD + ks * 16 + (lane >> 4) * 8) * 2);
#pragma unroll
        for (int n = 0; n < 5; ++n) {
            uint32_t b0, b1;
            ldsm_x2(b0, b1, ka + ((n * 8 + (lane & 7)) * AT_LD + ks * 16 + ((lane >> 3) & 1) * 8) * 2);
            mma16816(sc[n], a0, a1, a2, a3, b0, b1);
        }
    }
    const float scale = 0.08838834764831845f;
    int qi0 = warp * 16 + (lane >> 2), qi1 = qi0 + 8;
    float mx0 = -INFINITY, mx1 = -INFINITY;
#pragma unroll
    for (int n = 0; n < 5; ++n)
#pragma unroll
        for (int e = 0; e < 4; ++e) {
            int key = n * 8 + (lane & 3) * 2 + (e & 1);
            int qi = (e & 2) ? qi1 : qi0;
            float v = bf16r(bf16r(sc[n][e]) * scale);
            if (key >= 8 && key - 8 > qi) v = -INFINITY;
            sc[n][e] = v;
            if (e & 2) mx1 = fmaxf(mx1, v); else mx0 = fmaxf(mx0, v);
        }
    mx0 = fmaxf(mx0, __shfl_xor_sync(0xffffffffu, mx0, 1));
    mx0 = fmaxf(mx0, __shfl_xor_sync(0xffffffffu, mx0, 2));
    mx1 = fmaxf(mx1, __shfl_xor_sync(0xffffffffu, mx1, 1));
    mx1 = fmaxf(mx1, __shfl_xor_sync(0xffffffffu, mx1, 2));
    float s0 = 0.f, s1 = 0.f;
#pragma unroll
    for (int n = 0; n < 5; ++n)
#pragma unroll
        for (int e = 0; e < 4; ++e) {
            float ev = __expf(sc[n][e] - ((e & 2) ? mx1 : mx0));
            sc[n][e] = ev;
            if (e & 2) s1 += ev; else s0 += ev;
        }
    s0 += __shfl_xor_sync(0xffffffffu, s0, 1);
    s0 += __shfl_xor_sync(0xffffffffu, s0, 2);
    s1 += __shfl_xor_sync(0xffffffffu, s1, 1);
    s1 += __shfl_xor_sync(0xffffffffu, s1, 2);
    float i0 = 1.f / s0, i1 = 1.f / s1;
    uint32_t pa[3][4];
#pragma unroll
    for (int ks = 0; ks < 3; ++ks) {
        int n0 = 2 * ks, n1 = 2 * ks + 1;
        pa[ks][0] = pack_bf16(sc[n0][0] * i0, sc[n0][1] * i0);
        pa[ks][1] = pack_bf16(sc[n0][2] * i1, sc[n0][3] * i1);
        if (n1 < 5) {
            pa[ks][2] = pack_bf16(sc[n1][0] * i0, sc[n1][1] * i0);
            pa[ks][3] = pack_bf16(sc[n1][2] * i1, sc[n1][3] * i1);
        } else {
            pa[ks][2] = 0; pa[ks][3] = 0;
        }
    }
#pragma unroll
    for (int nb = 0; nb < 16; ++nb) {
        float o[4] = {0.f, 0.f, 0.f, 0.f};
#pragma unroll
        for (int ks = 0; ks < 3; ++ks) {
            uint32_t b0, b1;
            ldsm_x2_t(b0, b1, va + ((ks * 16 + (lane & 15)) * AT_LD + nb * 8) * 2);
            mma16816(o, pa[ks][0], pa[ks][1], pa[ks][2], pa[ks][3], b0, b1);
        }
        int col = h * DH_ + nb * 8 + (lane & 3) * 2;
        *reinterpret_cast<uint32_t*>(g_o + (size_t)(s * SEG_ + qi0) * HD_ + col) = pack_bf16(o[0], o[1]);
        *reinterpret_cast<uint32_t*>(g_o + (size_t)(s * SEG_ + qi1) * HD_ + col) = pack_bf16(o[2], o[3]);
    }
}

typedef CUresult (*EncodeFn)(CUtensorMap*, CUtensorMapDataType, cuuint32_t, void*, const cuuint64_t*,
                             const cuuint64_t*, const cuuint32_t*, const cuuint32_t*, CUtensorMapInterleave,
                             CUtensorMapSwizzle, CUtensorMapL2promotion, CUtensorMapFloatOOBfill);

EncodeFn get_encode() {
    static EncodeFn fn = nullptr;
    if (!fn) {
        void* p = nullptr;
        cudaDriverEntryPointQueryResult qr;
        cudaGetDriverEntryPoint("cuTensorMapEncodeTiled", &p, cudaEnableDefault, &qr);
        fn = (EncodeFn)p;
    }
    return fn;
}

CUtensorMap make_map(const void* ptr, int rows, int cols, int ld, int br, int bc) {
    CUtensorMap m;
    cuuint64_t dims[2] = {(cuuint64_t)cols, (cuuint64_t)rows};
    cuuint64_t strides[1] = {(cuuint64_t)ld * 2};
    cuuint32_t box[2] = {(cuuint32_t)bc, (cuuint32_t)br};
    cuuint32_t es[2] = {1, 1};
    get_encode()(&m, CU_TENSOR_MAP_DATA_TYPE_BFLOAT16, 2, const_cast<void*>(ptr), dims, strides, box, es,
                 CU_TENSOR_MAP_INTERLEAVE_NONE, CU_TENSOR_MAP_SWIZZLE_128B, CU_TENSOR_MAP_L2_PROMOTION_L2_128B,
                 CU_TENSOR_MAP_FLOAT_OOB_FILL_NONE);
    return m;
}

template <typename T>
T* sym_addr(const T& sym) {
    void* p = nullptr;
    cudaGetSymbolAddress(&p, sym);
    return (T*)p;
}

template <int NWG, int BN, int STAGES>
constexpr int gemm_smem() {
    return STAGES * (NWG * 64 * 64 * 2 + BN * 64 * 2) + 2 * STAGES * 8 + 1024;
}

template <int NWG, int BN, int STAGES, int EPI>
void launch_gemm(const CUtensorMap& a, const CUtensorMap& b, const EpiArgs& ea, int M, int N, int K, cudaStream_t st) {
    constexpr int smem = gemm_smem<NWG, BN, STAGES>();
    cudaFuncSetAttribute(gemm_kernel<NWG, BN, STAGES, EPI>, cudaFuncAttributeMaxDynamicSharedMemorySize, smem);
    cudaFuncSetAttribute(gemm_kernel<NWG, BN, STAGES, EPI>, cudaFuncAttributePreferredSharedMemoryCarveout, 100);
    dim3 grid((N + BN - 1) / BN, M / (64 * NWG));
    gemm_kernel<NWG, BN, STAGES, EPI><<<grid, NWG == 2 ? 288 : 128, smem, st>>>(a, b, ea, K);
}

template <int NWG, int BN, int STAGES>
void launch_qkv(const CUtensorMap& a, const TMaps3& b, const Out3& o3, int z0, int nz, unsigned* flag, cudaStream_t st) {
    constexpr int smem = gemm_smem<NWG, BN, STAGES>();
    cudaFuncSetAttribute(gemm_qkv_kernel<NWG, BN, STAGES>, cudaFuncAttributeMaxDynamicSharedMemorySize, smem);
    cudaFuncSetAttribute(gemm_qkv_kernel<NWG, BN, STAGES>, cudaFuncAttributePreferredSharedMemoryCarveout, 100);
    gemm_qkv_kernel<NWG, BN, STAGES><<<dim3(nz * (HD_ / BN), S_ / (64 * NWG)), NWG == 2 ? 288 : 128, smem, st>>>(a, b, o3, D_, z0, flag);
}

}

extern "C" void kernel_launch(void* const* d_in, const int* in_sizes, int n_in, void* d_out, int out_size) {
    const bf16* x = (const bf16*)d_in[0];
    const bf16* mem0 = (const bf16*)d_in[1];
    const bf16* Wq = (const bf16*)d_in[2];
    const bf16* Wk = (const bf16*)d_in[3];
    const bf16* Wv = (const bf16*)d_in[4];
    const bf16* Wo = (const bf16*)d_in[5];
    const bf16* w_in = (const bf16*)d_in[8];
    const bf16* w_sp = (const bf16*)d_in[9];
    const bf16* b_sp = (const bf16*)d_in[10];
    const bf16* w_out = (const bf16*)d_in[11];
    bf16* out = (bf16*)d_out;
    cudaStream_t st = cudaStreamPerThread;

    bf16* p_xn = (bf16*)sym_addr(g_xn);
    bf16* p_q = (bf16*)sym_addr(g_q);
    bf16* p_k = (bf16*)sym_addr(g_k);
    bf16* p_v = (bf16*)sym_addr(g_v);
    bf16* p_z = (bf16*)sym_addr(g_z);
    bf16* p_z2n = (bf16*)sym_addr(g_z2n);
    bf16* p_y = (bf16*)sym_addr(g_y);
    bf16* p_gg = (bf16*)sym_addr(g_gg);
    bf16* p_o = (bf16*)sym_addr(g_o);

    CUtensorMap tm_xn = make_map(p_xn, S_, D_, D_, 128, 64);
    CUtensorMap tm_xn_s = make_map(p_xn, S_, D_, D_, 64, 64);
    TMaps3 tm_w;
    tm_w.m[0] = make_map(Wq, D_, HD_, HD_, 64, 64);
    tm_w.m[1] = make_map(Wk, D_, HD_, HD_, 64, 64);
    tm_w.m[2] = make_map(Wv, D_, HD_, HD_, 64, 64);
    CUtensorMap tm_win = make_map(w_in, D_, F_, F_, 64, 64);
    CUtensorMap tm_wsp_s = make_map(w_sp, S_, S_, S_, 64, 64);
    CUtensorMap tm_z2n = make_map(p_z2n, S_, FH_, FH_, 64, 64);
    CUtensorMap tm_y_s = make_map(p_y, S_, FH_, FH_, 64, 64);
    CUtensorMap tm_wout = make_map(w_out, FH_, D_, D_, 64, 64);
    CUtensorMap tm_o = make_map(p_o, S_, HD_, HD_, 128, 64);
    CUtensorMap tm_wo = make_map(Wo, HD_, D_, D_, 64, 64);
    Out3 o3;
    o3.p[0] = p_q; o3.p[1] = p_k; o3.p[2] = p_v;

    static cudaStream_t st2 = nullptr;
    static cudaEvent_t ev_fork = nullptr, ev_join = nullptr;
    static cudaStream_t st_hi = nullptr;
    static cudaEvent_t ev_join_hi = nullptr;
    if (!st_hi) {
        int lo = 0, hi = 0;
        cudaDeviceGetStreamPriorityRange(&lo, &hi);
        cudaStreamCreateWithPriority(&st_hi, cudaStreamNonBlocking, hi);
        cudaEventCreateWithFlags(&ev_join_hi, cudaEventDisableTiming);
    }
    if (!st2) {
        cudaStreamCreateWithFlags(&st2, cudaStreamNonBlocking);
        cudaEventCreateWithFlags(&ev_fork, cudaEventDisableTiming);
        cudaEventCreateWithFlags(&ev_join, cudaEventDisableTiming);
    }

    unsigned* p_kvflag = (unsigned*)sym_addr(g_kvflag);
    unsigned* p_atflag = (unsigned*)sym_addr(g_atflag);
    CUtensorMap tm_o_s = make_map(p_o, S_, HD_, HD_, 64, 64);
    ln1_kernel<<<S_ / 8, 256, 0, st>>>(x);
    launch_qkv<2, 256, 4>(tm_xn, tm_w, o3, 1, 2, nullptr, st);
    cudaEventRecord(ev_fork, st);
    cudaStreamWaitEvent(st2, ev_fork, 0);
    cudaFuncSetAttribute(chain_kernel, cudaFuncAttributeMaxDynamicSharedMemorySize, CH_SMEM);
    cudaFuncSetAttribute(chain_kernel, cudaFuncAttributePreferredSharedMemoryCarveout, 100);
    cudaFuncSetAttribute(ln2_kernel, cudaFuncAttributePreferredSharedMemoryCarveout, 100);
    cudaFuncSetAttribute(attn_kernel, cudaFuncAttributePreferredSharedMemoryCarveout, 100);
    cudaStreamWaitEvent(st_hi, ev_fork, 0);
    chain_kernel<<<128, CH_T, CH_SMEM, st_hi>>>(Wq, Wk, Wv, Wo, mem0);
    cudaEventRecord(ev_join_hi, st_hi);
    {
        launch_qkv<1, 128, 2>(tm_xn_s, tm_w, o3, 0, 1, nullptr, st2);
        EpiArgs ez = {p_z, F_, nullptr, 0, nullptr, 0, nullptr, F_, nullptr, 0, nullptr};
        launch_gemm<1, 128, 2, EPI_GELU>(tm_xn_s, tm_win, ez, S_, F_, D_, st2);
        ln2_kernel<<<S_ / 8, 256, 0, st2>>>();
        EpiArgs ey = {p_y, FH_, p_z, F_, nullptr, 0, b_sp, FH_, nullptr, 0, nullptr};
        launch_gemm<1, 128, 2, EPI_GATE>(tm_wsp_s, tm_z2n, ey, S_, FH_, S_, st2);
        EpiArgs eg = {p_gg, D_, nullptr, 0, nullptr, 0, nullptr, D_, nullptr, 0, nullptr};
        launch_gemm<1, 128, 2, EPI_SILU>(tm_y_s, tm_wout, eg, S_, D_, 896, st2);
        cudaEventRecord(ev_join, st2);
    }
    cudaStreamWaitEvent(st, ev_join, 0);
    cudaStreamWaitEvent(st, ev_join_hi, 0);
    attn_kernel<<<NSEG_ * H_, 64, 0, st>>>();
    {
        EpiArgs ea = {out, D_, p_gg, D_, x, D_, nullptr, D_, nullptr, 0, nullptr};
        launch_gemm<2, 128, 4, EPI_FINAL>(tm_o, tm_wo, ea, S_, D_, HD_, st);
    }
}
```
